```python
import torch

def _softmax(x, axis=-1):
    return torch.softmax(x, dim=axis)
def _gelu(x):
    return torch.nn.functional.gelu(x, approximate="tanh")
def _silu(x):
    return torch.nn.functional.silu(x)
def _sigmoid(x):
    return torch.sigmoid(x)
def _layernorm(x, axis=-1, eps=1e-5):
    m = x.mean(dim=axis, keepdim=True)
    v = x.var(dim=axis, keepdim=True, unbiased=False)
    return (x - m) / torch.sqrt(v + eps)
def _scatter_add(tgt, idx, src, axis=0):
    return tgt.clone().index_add_(axis, idx, src)
def _segment_sum(src, seg, n):
    out = torch.zeros((n,) + src.shape[1:], dtype=src.dtype)
    return out.index_add_(0, seg, src)
def _pad(x, pw):
    flat = tuple(v for pair in reversed(pw) for v in pair)
    return torch.nn.functional.pad(x, flat)

kernel_name = 'standalone__mha_block_cached__near_ridge'

def setup_inputs():

    _w = (lambda a: (lambda t: t.to(torch.bfloat16) if t.is_floating_point() else t)(torch.as_tensor(a)))
    B, Sq, D = 8, 224, 512
    H, Sk, Dh = 32, 1024, 128
    return {
        "x": _w((lambda *s: torch.randn(*s, dtype=torch.bfloat16) * 0.8)(B, Sq, D)),
        "k_cache": _w((lambda *s: torch.randn(*s, dtype=torch.bfloat16) * 0.8)(B, H, Sk, Dh)),
        "v_cache": _w((lambda *s: torch.randn(*s, dtype=torch.bfloat16) * 0.05)(B, H, Sk, Dh)),
        "wq": _w((lambda *s: torch.randn(*s, dtype=torch.bfloat16) * 0.8)(D, H * Dh) * (D ** -0.5)),
        "wo": _w((lambda *s: torch.randn(*s, dtype=torch.bfloat16) * 0.05)(H * Dh, D) * ((H * Dh) ** -0.5)),
    }

def reference(x, k_cache, v_cache, wq, wo):
    B, Sq, D = x.shape
    H, Dh = 32, 128
    q = (lambda x, *d: x.permute(*d))((x @ wq).reshape(B, Sq, H, Dh), 0, 2, 1, 3)
    scores = torch.einsum("bhqd,bhkd->bhqk", q, k_cache) * (Dh ** -0.5)
    p = _softmax(scores, axis=-1)
    o = torch.einsum("bhqk,bhkd->bhqd", p, v_cache)
    return (lambda x, *d: x.permute(*d))(o, 0, 2, 1, 3).reshape(B, Sq, H * Dh) @ wo
```

```cpp
#include <cuda_runtime.h>
#include <cuda_bf16.h>
#include <cuda.h>
#include <stdint.h>
#include <type_traits>

namespace {

constexpr int SLOT       = 16384;
constexpr int NSLOT      = 7;
constexpr int QO_OFF     = 114688;
constexpr int QO_HALF    = 28672;
constexpr int QO_HEAD    = 57344;
constexpr int P1_OFF     = 45056;
constexpr int P1_STAGE   = 61440;
constexpr int BAR_OFF    = 229376;
constexpr int ZERO_OFF   = BAR_OFF + 256;
constexpr int SMEM_BYTES = ZERO_OFF + 2048;
constexpr uint32_t SB    = 1024;
constexpr int XCH        = 14336;
constexpr uint32_t META_BITS = 0x44EEEE44u;

constexpr unsigned long long pf_cum(unsigned t) {
  unsigned long long r = 0; int s = 0;
  for (int i = 0; i < 8; i++) { s += (t >> (28 - 4 * i)) & 15; r |= (unsigned long long)s << (5 * i + 5); }
  return r;
}
constexpr unsigned long long PFCUM = pf_cum(0x01212134);

constexpr int B_FULL = 0;
constexpr int B_P1L  = 4;
constexpr int B_WE   = 6;
constexpr int B_O1   = 9;
constexpr int B_P1E  = 10;
constexpr int B_K0   = 13;
constexpr int B_X    = 14;
constexpr int B_XF   = 16;
constexpr int B_WF   = 18;
constexpr int B_P1F  = 21;
constexpr int B_META = 24, B_EPOCH = 25;

__device__ __align__(128) unsigned char g_xbuf[128 * 4 * XCH];
__device__ unsigned g_zcnt[16];

__device__ __forceinline__ uint32_t smem_u32(const void* p) { return (uint32_t)__cvta_generic_to_shared(p); }
__device__ __forceinline__ uint32_t rank_off() { return (blockIdx.x & 1u) << 24; }
__device__ __forceinline__ void mbar_init(uint32_t bar, int cnt) { asm volatile("mbarrier.init.shared::cta.b64 [%0], %1;" ::"r"(bar + rank_off()), "r"(cnt) : "memory"); }
__device__ __forceinline__ void mbar_expect_tx(uint32_t bar, uint32_t bytes) { asm volatile("mbarrier.arrive.expect_tx.shared::cta.b64 _, [%0], %1;" ::"r"(bar + rank_off()), "r"(bytes) : "memory"); }
__device__ __forceinline__ void mbar_arrive(uint32_t bar) { asm volatile("mbarrier.arrive.shared::cta.b64 _, [%0];" ::"r"(bar + rank_off()) : "memory"); }
__device__ __forceinline__ void mbar_wait(uint32_t bar, uint32_t parity) {
  asm volatile("{\n.reg .pred p;\nWAIT_%=:\nmbarrier.try_wait.parity.shared::cta.b64 p, [%0], %1;\n@p bra DONE_%=;\nbra WAIT_%=;\nDONE_%=:\n}" ::"r"(bar + rank_off()), "r"(parity) : "memory");
}
__device__ __forceinline__ bool mbar_test(uint32_t bar, uint32_t parity) {
  uint32_t ok; asm volatile("{\n.reg .pred p;\nmbarrier.try_wait.parity.shared::cta.b64 p, [%1], %2;\nselp.u32 %0, 1, 0, p;\n}" : "=r"(ok) : "r"(bar + rank_off()), "r"(parity) : "memory"); return ok != 0;
}
__device__ __forceinline__ void tma2d(uint32_t dst, const CUtensorMap* m, int c0, int c1, uint32_t bar) {
  asm volatile("cp.async.bulk.tensor.2d.shared::cluster.global.mbarrier::complete_tx::bytes [%0], [%1, {%3, %4}], [%2];" ::"r"(dst + rank_off()), "l"(m), "r"(bar + rank_off()), "r"(c0), "r"(c1) : "memory");
}
__device__ __forceinline__ void tma2d_mc(uint32_t dst, const CUtensorMap* m, int c0, int c1, uint32_t bar) {
  asm volatile("cp.async.bulk.tensor.2d.shared::cluster.global.mbarrier::complete_tx::bytes.multicast::cluster [%0], [%1, {%3, %4}], [%2], %5;" ::"r"(dst + rank_off()), "l"(m), "r"(bar + rank_off()), "r"(c0), "r"(c1), "h"((uint16_t)3) : "memory");
}
__device__ __forceinline__ void mbar_arrive_peer(uint32_t bar) { asm volatile("mbarrier.arrive.shared::cluster.b64 _, [%0];" ::"r"(bar + (rank_off() ^ (1u << 24))) : "memory"); }
__device__ __forceinline__ void tma3d(uint32_t dst, const CUtensorMap* m, int c0, int c1, int c2, uint32_t bar) {
  asm volatile("cp.async.bulk.tensor.3d.shared::cluster.global.mbarrier::complete_tx::bytes [%0], [%1, {%3, %4, %5}], [%2];" ::"r"(dst + rank_off()), "l"(m), "r"(bar + rank_off()), "r"(c0), "r"(c1), "r"(c2) : "memory");
}
__device__ __forceinline__ void tma_kv(uint32_t dst, const CUtensorMap* m, int grp, uint32_t bar, uint64_t pol) {
  asm volatile("cp.async.bulk.tensor.4d.shared::cluster.global.mbarrier::complete_tx::bytes.L2::cache_hint [%0], [%1, {%3, %3, %3, %4}], [%2], %5;" ::"r"(dst + rank_off()), "l"(m), "r"(bar + rank_off()), "r"(0), "r"(grp), "l"(pol) : "memory");
}
constexpr uint64_t POL_EVICT_FIRST = 0x12F0000000000000ull;
__device__ __forceinline__ void tma_red2d(const CUtensorMap* m, int c0, int c1, uint32_t src) {
  asm volatile("cp.reduce.async.bulk.tensor.2d.global.shared::cta.add.tile.bulk_group [%0, {%2, %3}], [%1];" ::"l"(m), "r"(src + rank_off()), "r"(c0), "r"(c1) : "memory");
}
__device__ __forceinline__ void bulk_store(void* dst, uint32_t src, uint32_t bytes) { asm volatile("cp.async.bulk.global.shared::cta.bulk_group [%0], [%1], %2;" ::"l"(dst), "r"(src + rank_off()), "r"(bytes) : "memory"); }
__device__ __forceinline__ void bulk_load(uint32_t dst, const void* src, uint32_t bytes, uint32_t bar) { asm volatile("cp.async.bulk.shared::cluster.global.mbarrier::complete_tx::bytes [%0], [%1], %2, [%3];" ::"r"(dst + rank_off()), "l"(src), "r"(bytes), "r"(bar + rank_off()) : "memory"); }
__device__ __forceinline__ void bulk_commit() { asm volatile("cp.async.bulk.commit_group;" ::: "memory"); }
__device__ __forceinline__ unsigned ld_acquire(const unsigned* p) { unsigned v; asm volatile("ld.acquire.gpu.global.u32 %0, [%1];" : "=r"(v) : "l"(p) : "memory"); return v; }
__device__ __forceinline__ unsigned ld_smem(uint32_t a) { unsigned v; asm volatile("ld.volatile.shared.u32 %0, [%1];" : "=r"(v) : "r"(a + rank_off()) : "memory"); return v; }
__device__ __forceinline__ void spin_until(const unsigned* p, unsigned target) {
  for (int it = 0; it < (1 << 22) && (int)(ld_acquire(p) - target) < 0; it++) {}
}
__device__ __forceinline__ void l2_prefetch(const void* p, uint32_t bytes) { asm volatile("cp.async.bulk.prefetch.L2.global [%0], %1;" ::"l"(p), "r"(bytes) : "memory"); }
__device__ __forceinline__ void fence_async() { asm volatile("fence.proxy.async.shared::cta;" ::: "memory"); }
__device__ __forceinline__ void bar_sync(int id, int n) { asm volatile("bar.sync %0, %1;" ::"r"(id), "r"(n) : "memory"); }
__device__ __forceinline__ void bar_arrive(int id, int n) { asm volatile("bar.arrive %0, %1;" ::"r"(id), "r"(n) : "memory"); }
__device__ __forceinline__ bool elect_one() {
  uint32_t p; asm volatile("{\n.reg .pred P;\nelect.sync _|P, 0xffffffff;\nselp.u32 %0, 1, 0, P;\n}" : "=r"(p)); return p != 0;
}
__device__ __forceinline__ uint32_t pack_bf16(float lo, float hi) { uint32_t r; asm("cvt.rn.bf16x2.f32 %0, %1, %2;" : "=r"(r) : "f"(hi), "f"(lo)); return r; }
__device__ __forceinline__ float ex2(float x) { float y; asm("ex2.approx.ftz.f32 %0, %1;" : "=f"(y) : "f"(x)); return y; }
__device__ __forceinline__ float rcp(float x) { float y; asm("rcp.approx.ftz.f32 %0, %1;" : "=f"(y) : "f"(x)); return y; }
__device__ __forceinline__ void stsm4(uint32_t a, uint32_t r0, uint32_t r1, uint32_t r2, uint32_t r3) {
  asm volatile("stmatrix.sync.aligned.m8n8.x4.shared.b16 [%0], {%1,%2,%3,%4};" ::"r"(a + rank_off()), "r"(r0), "r"(r1), "r"(r2), "r"(r3) : "memory");
}
__device__ __forceinline__ void stsm4t(uint32_t a, uint32_t r0, uint32_t r1, uint32_t r2, uint32_t r3) {
  asm volatile("stmatrix.sync.aligned.m8n8.x4.trans.shared.b16 [%0], {%1,%2,%3,%4};" ::"r"(a + rank_off()), "r"(r0), "r"(r1), "r"(r2), "r"(r3) : "memory");
}
__host__ __device__ constexpr uint32_t dlo(uint32_t off, uint32_t lbo) { return ((SB + off) >> 4) | ((lbo >> 4) << 16); }
#define WG_FENCE()  asm volatile("wgmma.fence.sync.aligned;" ::: "memory")
#define WG_COMMIT() asm volatile("wgmma.commit_group.sync.aligned;" ::: "memory")
#define WG_WAIT(n)  asm volatile("wgmma.wait_group.sync.aligned %0;" ::"n"(n) : "memory")
template <int N> __device__ __forceinline__ void fence_regs(float (&r)[N]) {
#pragma unroll
  for (int i = 0; i < N; i++) asm volatile("" : "+f"(r[i])::"memory");
}
template <int N> __device__ __forceinline__ void fence_regs(uint32_t (&r)[N]) {
#pragma unroll
  for (int i = 0; i < N; i++) asm volatile("" : "+r"(r[i])::"memory");
}

__device__ __forceinline__ void mma_proj_pred(float (&d)[112], uint32_t da, uint32_t db, int sd) {
  asm volatile("{\n.reg .pred p;\n.reg .b64 da, db;\nmov.b64 da, {%112, 0x40000040};\nmov.b64 db, {%113, 0x40000040};\nsetp.ne.b32 p, %114, 0;\n"
    "wgmma.mma_async.sync.aligned.m64n224k16.f32.bf16.bf16 "
    "{%0, %1, %2, %3, %4, %5, %6, %7, %8, %9, %10, %11, %12, %13, %14, %15, %16, %17, %18, %19, %20, %21, %22, %23, %24, %25, %26, %27, %28, %29, %30, %31, %32, %33, %34, %35, %36, %37, %38, %39, %40, %41, %42, %43, %44, %45, %46, %47, %48, %49, %50, %51, %52, %53, %54, %55, %56, %57, %58, %59, %60, %61, %62, %63, %64, %65, %66, %67, %68, %69, %70, %71, %72, %73, %74, %75, %76, %77, %78, %79, %80, %81, %82, %83, %84, %85, %86, %87, %88, %89, %90, %91, %92, %93, %94, %95, %96, %97, %98, %99, %100, %101, %102, %103, %104, %105, %106, %107, %108, %109, %110, %111}, "
    "da, db, p, 1, 1, 1, 0;\n}\n"
    : "+f"(d[0]), "+f"(d[1]), "+f"(d[2]), "+f"(d[3]), "+f"(d[4]), "+f"(d[5]), "+f"(d[6]), "+f"(d[7]), "+f"(d[8]), "+f"(d[9]), "+f"(d[10]), "+f"(d[11]), "+f"(d[12]), "+f"(d[13]), "+f"(d[14]), "+f"(d[15]), "+f"(d[16]), "+f"(d[17]), "+f"(d[18]), "+f"(d[19]), "+f"(d[20]), "+f"(d[21]), "+f"(d[22]), "+f"(d[23]), "+f"(d[24]), "+f"(d[25]), "+f"(d[26]), "+f"(d[27]), "+f"(d[28]), "+f"(d[29]), "+f"(d[30]), "+f"(d[31]), "+f"(d[32]), "+f"(d[33]), "+f"(d[34]), "+f"(d[35]), "+f"(d[36]), "+f"(d[37]), "+f"(d[38]), "+f"(d[39]), "+f"(d[40]), "+f"(d[41]), "+f"(d[42]), "+f"(d[43]), "+f"(d[44]), "+f"(d[45]), "+f"(d[46]), "+f"(d[47]), "+f"(d[48]), "+f"(d[49]), "+f"(d[50]), "+f"(d[51]), "+f"(d[52]), "+f"(d[53]), "+f"(d[54]), "+f"(d[55]), "+f"(d[56]), "+f"(d[57]), "+f"(d[58]), "+f"(d[59]), "+f"(d[60]), "+f"(d[61]), "+f"(d[62]), "+f"(d[63]), "+f"(d[64]), "+f"(d[65]), "+f"(d[66]), "+f"(d[67]), "+f"(d[68]), "+f"(d[69]), "+f"(d[70]), "+f"(d[71]), "+f"(d[72]), "+f"(d[73]), "+f"(d[74]), "+f"(d[75]), "+f"(d[76]), "+f"(d[77]), "+f"(d[78]), "+f"(d[79]), "+f"(d[80]), "+f"(d[81]), "+f"(d[82]), "+f"(d[83]), "+f"(d[84]), "+f"(d[85]), "+f"(d[86]), "+f"(d[87]), "+f"(d[88]), "+f"(d[89]), "+f"(d[90]), "+f"(d[91]), "+f"(d[92]), "+f"(d[93]), "+f"(d[94]), "+f"(d[95]), "+f"(d[96]), "+f"(d[97]), "+f"(d[98]), "+f"(d[99]), "+f"(d[100]), "+f"(d[101]), "+f"(d[102]), "+f"(d[103]), "+f"(d[104]), "+f"(d[105]), "+f"(d[106]), "+f"(d[107]), "+f"(d[108]), "+f"(d[109]), "+f"(d[110]), "+f"(d[111])
    : "r"(da), "r"(db), "r"(sd));
}
__device__ __forceinline__ void mma_proj(float (&d)[112], uint32_t da, uint32_t db) {
  asm volatile("{\n.reg .pred p;\n.reg .b64 da, db;\nmov.b64 da, {%112, 0x40000040};\nmov.b64 db, {%113, 0x40000040};\n"
    "wgmma.mma_async.sync.aligned.m64n224k16.f32.bf16.bf16 "
    "{%0, %1, %2, %3, %4, %5, %6, %7, %8, %9, %10, %11, %12, %13, %14, %15, %16, %17, %18, %19, %20, %21, %22, %23, %24, %25, %26, %27, %28, %29, %30, %31, %32, %33, %34, %35, %36, %37, %38, %39, %40, %41, %42, %43, %44, %45, %46, %47, %48, %49, %50, %51, %52, %53, %54, %55, %56, %57, %58, %59, %60, %61, %62, %63, %64, %65, %66, %67, %68, %69, %70, %71, %72, %73, %74, %75, %76, %77, %78, %79, %80, %81, %82, %83, %84, %85, %86, %87, %88, %89, %90, %91, %92, %93, %94, %95, %96, %97, %98, %99, %100, %101, %102, %103, %104, %105, %106, %107, %108, %109, %110, %111}, "
    "da, db, 1, 1, 1, 1, 0;\n}\n"
    : "+f"(d[0]), "+f"(d[1]), "+f"(d[2]), "+f"(d[3]), "+f"(d[4]), "+f"(d[5]), "+f"(d[6]), "+f"(d[7]), "+f"(d[8]), "+f"(d[9]), "+f"(d[10]), "+f"(d[11]), "+f"(d[12]), "+f"(d[13]), "+f"(d[14]), "+f"(d[15]), "+f"(d[16]), "+f"(d[17]), "+f"(d[18]), "+f"(d[19]), "+f"(d[20]), "+f"(d[21]), "+f"(d[22]), "+f"(d[23]), "+f"(d[24]), "+f"(d[25]), "+f"(d[26]), "+f"(d[27]), "+f"(d[28]), "+f"(d[29]), "+f"(d[30]), "+f"(d[31]), "+f"(d[32]), "+f"(d[33]), "+f"(d[34]), "+f"(d[35]), "+f"(d[36]), "+f"(d[37]), "+f"(d[38]), "+f"(d[39]), "+f"(d[40]), "+f"(d[41]), "+f"(d[42]), "+f"(d[43]), "+f"(d[44]), "+f"(d[45]), "+f"(d[46]), "+f"(d[47]), "+f"(d[48]), "+f"(d[49]), "+f"(d[50]), "+f"(d[51]), "+f"(d[52]), "+f"(d[53]), "+f"(d[54]), "+f"(d[55]), "+f"(d[56]), "+f"(d[57]), "+f"(d[58]), "+f"(d[59]), "+f"(d[60]), "+f"(d[61]), "+f"(d[62]), "+f"(d[63]), "+f"(d[64]), "+f"(d[65]), "+f"(d[66]), "+f"(d[67]), "+f"(d[68]), "+f"(d[69]), "+f"(d[70]), "+f"(d[71]), "+f"(d[72]), "+f"(d[73]), "+f"(d[74]), "+f"(d[75]), "+f"(d[76]), "+f"(d[77]), "+f"(d[78]), "+f"(d[79]), "+f"(d[80]), "+f"(d[81]), "+f"(d[82]), "+f"(d[83]), "+f"(d[84]), "+f"(d[85]), "+f"(d[86]), "+f"(d[87]), "+f"(d[88]), "+f"(d[89]), "+f"(d[90]), "+f"(d[91]), "+f"(d[92]), "+f"(d[93]), "+f"(d[94]), "+f"(d[95]), "+f"(d[96]), "+f"(d[97]), "+f"(d[98]), "+f"(d[99]), "+f"(d[100]), "+f"(d[101]), "+f"(d[102]), "+f"(d[103]), "+f"(d[104]), "+f"(d[105]), "+f"(d[106]), "+f"(d[107]), "+f"(d[108]), "+f"(d[109]), "+f"(d[110]), "+f"(d[111])
    : "r"(da), "r"(db));
}
__device__ __forceinline__ void mma_out(float (&d)[56], uint32_t da, uint32_t db) {
  asm volatile("{\n.reg .pred p;\n.reg .b64 da, db;\nmov.b64 da, {%56, 0x40000040};\nmov.b64 db, {%57, 0x40000040};\n"
    "wgmma.mma_async.sync.aligned.m64n112k16.f32.bf16.bf16 "
    "{%0, %1, %2, %3, %4, %5, %6, %7, %8, %9, %10, %11, %12, %13, %14, %15, %16, %17, %18, %19, %20, %21, %22, %23, %24, %25, %26, %27, %28, %29, %30, %31, %32, %33, %34, %35, %36, %37, %38, %39, %40, %41, %42, %43, %44, %45, %46, %47, %48, %49, %50, %51, %52, %53, %54, %55}, "
    "da, db, 1, 1, 1, 1, 0;\n}\n"
    : "+f"(d[0]), "+f"(d[1]), "+f"(d[2]), "+f"(d[3]), "+f"(d[4]), "+f"(d[5]), "+f"(d[6]), "+f"(d[7]), "+f"(d[8]), "+f"(d[9]), "+f"(d[10]), "+f"(d[11]), "+f"(d[12]), "+f"(d[13]), "+f"(d[14]), "+f"(d[15]), "+f"(d[16]), "+f"(d[17]), "+f"(d[18]), "+f"(d[19]), "+f"(d[20]), "+f"(d[21]), "+f"(d[22]), "+f"(d[23]), "+f"(d[24]), "+f"(d[25]), "+f"(d[26]), "+f"(d[27]), "+f"(d[28]), "+f"(d[29]), "+f"(d[30]), "+f"(d[31]), "+f"(d[32]), "+f"(d[33]), "+f"(d[34]), "+f"(d[35]), "+f"(d[36]), "+f"(d[37]), "+f"(d[38]), "+f"(d[39]), "+f"(d[40]), "+f"(d[41]), "+f"(d[42]), "+f"(d[43]), "+f"(d[44]), "+f"(d[45]), "+f"(d[46]), "+f"(d[47]), "+f"(d[48]), "+f"(d[49]), "+f"(d[50]), "+f"(d[51]), "+f"(d[52]), "+f"(d[53]), "+f"(d[54]), "+f"(d[55])
    : "r"(da), "r"(db));
}
__device__ __forceinline__ void mma_out_pred(float (&d)[56], uint32_t da, uint32_t db, int sd) {
  asm volatile("{\n.reg .pred p;\n.reg .b64 da, db;\nmov.b64 da, {%56, 0x40000040};\nmov.b64 db, {%57, 0x40000040};\nsetp.ne.b32 p, %58, 0;\n"
    "wgmma.mma_async.sync.aligned.m64n112k16.f32.bf16.bf16 "
    "{%0, %1, %2, %3, %4, %5, %6, %7, %8, %9, %10, %11, %12, %13, %14, %15, %16, %17, %18, %19, %20, %21, %22, %23, %24, %25, %26, %27, %28, %29, %30, %31, %32, %33, %34, %35, %36, %37, %38, %39, %40, %41, %42, %43, %44, %45, %46, %47, %48, %49, %50, %51, %52, %53, %54, %55}, "
    "da, db, p, 1, 1, 1, 0;\n}\n"
    : "+f"(d[0]), "+f"(d[1]), "+f"(d[2]), "+f"(d[3]), "+f"(d[4]), "+f"(d[5]), "+f"(d[6]), "+f"(d[7]), "+f"(d[8]), "+f"(d[9]), "+f"(d[10]), "+f"(d[11]), "+f"(d[12]), "+f"(d[13]), "+f"(d[14]), "+f"(d[15]), "+f"(d[16]), "+f"(d[17]), "+f"(d[18]), "+f"(d[19]), "+f"(d[20]), "+f"(d[21]), "+f"(d[22]), "+f"(d[23]), "+f"(d[24]), "+f"(d[25]), "+f"(d[26]), "+f"(d[27]), "+f"(d[28]), "+f"(d[29]), "+f"(d[30]), "+f"(d[31]), "+f"(d[32]), "+f"(d[33]), "+f"(d[34]), "+f"(d[35]), "+f"(d[36]), "+f"(d[37]), "+f"(d[38]), "+f"(d[39]), "+f"(d[40]), "+f"(d[41]), "+f"(d[42]), "+f"(d[43]), "+f"(d[44]), "+f"(d[45]), "+f"(d[46]), "+f"(d[47]), "+f"(d[48]), "+f"(d[49]), "+f"(d[50]), "+f"(d[51]), "+f"(d[52]), "+f"(d[53]), "+f"(d[54]), "+f"(d[55])
    : "r"(da), "r"(db), "r"(sd));
}
__device__ __forceinline__ void mma_kv_qk64_init(float (&d)[32], uint32_t da, uint32_t db) {
  asm volatile("{\n.reg .pred p;\n.reg .b64 da, db;\nmov.b64 da, {%32, 0x40000040};\nmov.b64 db, {%33, 0x40000080};\n"
    "wgmma.mma_async.sync.aligned.m64n64k16.f32.bf16.bf16 "
    "{%0, %1, %2, %3, %4, %5, %6, %7, %8, %9, %10, %11, %12, %13, %14, %15, %16, %17, %18, %19, %20, %21, %22, %23, %24, %25, %26, %27, %28, %29, %30, %31}, "
    "da, db, 0, 1, 1, 0, 0;\n}\n"
    : "=f"(d[0]), "=f"(d[1]), "=f"(d[2]), "=f"(d[3]), "=f"(d[4]), "=f"(d[5]), "=f"(d[6]), "=f"(d[7]), "=f"(d[8]), "=f"(d[9]), "=f"(d[10]), "=f"(d[11]), "=f"(d[12]), "=f"(d[13]), "=f"(d[14]), "=f"(d[15]), "=f"(d[16]), "=f"(d[17]), "=f"(d[18]), "=f"(d[19]), "=f"(d[20]), "=f"(d[21]), "=f"(d[22]), "=f"(d[23]), "=f"(d[24]), "=f"(d[25]), "=f"(d[26]), "=f"(d[27]), "=f"(d[28]), "=f"(d[29]), "=f"(d[30]), "=f"(d[31])
    : "r"(da), "r"(db));
}
__device__ __forceinline__ void mma_kv_qk64(float (&d)[32], uint32_t da, uint32_t db) {
  asm volatile("{\n.reg .pred p;\n.reg .b64 da, db;\nmov.b64 da, {%32, 0x40000040};\nmov.b64 db, {%33, 0x40000080};\n"
    "wgmma.mma_async.sync.aligned.m64n64k16.f32.bf16.bf16 "
    "{%0, %1, %2, %3, %4, %5, %6, %7, %8, %9, %10, %11, %12, %13, %14, %15, %16, %17, %18, %19, %20, %21, %22, %23, %24, %25, %26, %27, %28, %29, %30, %31}, "
    "da, db, 1, 1, 1, 0, 0;\n}\n"
    : "+f"(d[0]), "+f"(d[1]), "+f"(d[2]), "+f"(d[3]), "+f"(d[4]), "+f"(d[5]), "+f"(d[6]), "+f"(d[7]), "+f"(d[8]), "+f"(d[9]), "+f"(d[10]), "+f"(d[11]), "+f"(d[12]), "+f"(d[13]), "+f"(d[14]), "+f"(d[15]), "+f"(d[16]), "+f"(d[17]), "+f"(d[18]), "+f"(d[19]), "+f"(d[20]), "+f"(d[21]), "+f"(d[22]), "+f"(d[23]), "+f"(d[24]), "+f"(d[25]), "+f"(d[26]), "+f"(d[27]), "+f"(d[28]), "+f"(d[29]), "+f"(d[30]), "+f"(d[31])
    : "r"(da), "r"(db));
}
__device__ __forceinline__ void mma_kv_qk64_sp_init(float (&d)[32], uint32_t da, uint32_t db, uint32_t meta) {
  asm volatile("{\n.reg .pred p;\n.reg .b64 da, db;\nmov.b64 da, {%32, 0x80000020};\nmov.b64 db, {%33, 0x40000080};\n"
    "wgmma.mma_async.sp.sync.aligned.m64n64k32.f32.bf16.bf16 "
    "{%0, %1, %2, %3, %4, %5, %6, %7, %8, %9, %10, %11, %12, %13, %14, %15, %16, %17, %18, %19, %20, %21, %22, %23, %24, %25, %26, %27, %28, %29, %30, %31}, "
    "da, db, %34, 0, 0, 1, 1, 0, 0;\n}\n"
    : "=f"(d[0]), "=f"(d[1]), "=f"(d[2]), "=f"(d[3]), "=f"(d[4]), "=f"(d[5]), "=f"(d[6]), "=f"(d[7]), "=f"(d[8]), "=f"(d[9]), "=f"(d[10]), "=f"(d[11]), "=f"(d[12]), "=f"(d[13]), "=f"(d[14]), "=f"(d[15]), "=f"(d[16]), "=f"(d[17]), "=f"(d[18]), "=f"(d[19]), "=f"(d[20]), "=f"(d[21]), "=f"(d[22]), "=f"(d[23]), "=f"(d[24]), "=f"(d[25]), "=f"(d[26]), "=f"(d[27]), "=f"(d[28]), "=f"(d[29]), "=f"(d[30]), "=f"(d[31])
    : "r"(da), "r"(db), "r"(meta));
}
__device__ __forceinline__ void mma_kv_qk64_sp(float (&d)[32], uint32_t da, uint32_t db, uint32_t meta) {
  asm volatile("{\n.reg .pred p;\n.reg .b64 da, db;\nmov.b64 da, {%32, 0x80000020};\nmov.b64 db, {%33, 0x40000080};\n"
    "wgmma.mma_async.sp.sync.aligned.m64n64k32.f32.bf16.bf16 "
    "{%0, %1, %2, %3, %4, %5, %6, %7, %8, %9, %10, %11, %12, %13, %14, %15, %16, %17, %18, %19, %20, %21, %22, %23, %24, %25, %26, %27, %28, %29, %30, %31}, "
    "da, db, %34, 0, 1, 1, 1, 0, 0;\n}\n"
    : "+f"(d[0]), "+f"(d[1]), "+f"(d[2]), "+f"(d[3]), "+f"(d[4]), "+f"(d[5]), "+f"(d[6]), "+f"(d[7]), "+f"(d[8]), "+f"(d[9]), "+f"(d[10]), "+f"(d[11]), "+f"(d[12]), "+f"(d[13]), "+f"(d[14]), "+f"(d[15]), "+f"(d[16]), "+f"(d[17]), "+f"(d[18]), "+f"(d[19]), "+f"(d[20]), "+f"(d[21]), "+f"(d[22]), "+f"(d[23]), "+f"(d[24]), "+f"(d[25]), "+f"(d[26]), "+f"(d[27]), "+f"(d[28]), "+f"(d[29]), "+f"(d[30]), "+f"(d[31])
    : "r"(da), "r"(db), "r"(meta));
}
__device__ __forceinline__ void mma_kv_pv_pred(float (&d)[64], uint32_t a0, uint32_t a1, uint32_t a2, uint32_t a3, uint32_t db, int sd) {
  asm volatile("{\n.reg .pred p;\n.reg .b64 da, db;\nmov.b64 db, {%68, 0x40000080};\nsetp.ne.b32 p, %69, 0;\n"
    "wgmma.mma_async.sync.aligned.m64n128k16.f32.bf16.bf16 "
    "{%0, %1, %2, %3, %4, %5, %6, %7, %8, %9, %10, %11, %12, %13, %14, %15, %16, %17, %18, %19, %20, %21, %22, %23, %24, %25, %26, %27, %28, %29, %30, %31, %32, %33, %34, %35, %36, %37, %38, %39, %40, %41, %42, %43, %44, %45, %46, %47, %48, %49, %50, %51, %52, %53, %54, %55, %56, %57, %58, %59, %60, %61, %62, %63}, "
    "{%64,%65,%66,%67}, db, p, 1, 1, 1;\n}\n"
    : "+f"(d[0]), "+f"(d[1]), "+f"(d[2]), "+f"(d[3]), "+f"(d[4]), "+f"(d[5]), "+f"(d[6]), "+f"(d[7]), "+f"(d[8]), "+f"(d[9]), "+f"(d[10]), "+f"(d[11]), "+f"(d[12]), "+f"(d[13]), "+f"(d[14]), "+f"(d[15]), "+f"(d[16]), "+f"(d[17]), "+f"(d[18]), "+f"(d[19]), "+f"(d[20]), "+f"(d[21]), "+f"(d[22]), "+f"(d[23]), "+f"(d[24]), "+f"(d[25]), "+f"(d[26]), "+f"(d[27]), "+f"(d[28]), "+f"(d[29]), "+f"(d[30]), "+f"(d[31]), "+f"(d[32]), "+f"(d[33]), "+f"(d[34]), "+f"(d[35]), "+f"(d[36]), "+f"(d[37]), "+f"(d[38]), "+f"(d[39]), "+f"(d[40]), "+f"(d[41]), "+f"(d[42]), "+f"(d[43]), "+f"(d[44]), "+f"(d[45]), "+f"(d[46]), "+f"(d[47]), "+f"(d[48]), "+f"(d[49]), "+f"(d[50]), "+f"(d[51]), "+f"(d[52]), "+f"(d[53]), "+f"(d[54]), "+f"(d[55]), "+f"(d[56]), "+f"(d[57]), "+f"(d[58]), "+f"(d[59]), "+f"(d[60]), "+f"(d[61]), "+f"(d[62]), "+f"(d[63])
    : "r"(a0), "r"(a1), "r"(a2), "r"(a3), "r"(db), "r"(sd));
}
__device__ __forceinline__ void mma_kv_pv(float (&d)[64], uint32_t a0, uint32_t a1, uint32_t a2, uint32_t a3, uint32_t db) {
  asm volatile("{\n.reg .pred p;\n.reg .b64 da, db;\nmov.b64 db, {%68, 0x40000080};\n"
    "wgmma.mma_async.sync.aligned.m64n128k16.f32.bf16.bf16 "
    "{%0, %1, %2, %3, %4, %5, %6, %7, %8, %9, %10, %11, %12, %13, %14, %15, %16, %17, %18, %19, %20, %21, %22, %23, %24, %25, %26, %27, %28, %29, %30, %31, %32, %33, %34, %35, %36, %37, %38, %39, %40, %41, %42, %43, %44, %45, %46, %47, %48, %49, %50, %51, %52, %53, %54, %55, %56, %57, %58, %59, %60, %61, %62, %63}, "
    "{%64,%65,%66,%67}, db, 1, 1, 1, 1;\n}\n"
    : "+f"(d[0]), "+f"(d[1]), "+f"(d[2]), "+f"(d[3]), "+f"(d[4]), "+f"(d[5]), "+f"(d[6]), "+f"(d[7]), "+f"(d[8]), "+f"(d[9]), "+f"(d[10]), "+f"(d[11]), "+f"(d[12]), "+f"(d[13]), "+f"(d[14]), "+f"(d[15]), "+f"(d[16]), "+f"(d[17]), "+f"(d[18]), "+f"(d[19]), "+f"(d[20]), "+f"(d[21]), "+f"(d[22]), "+f"(d[23]), "+f"(d[24]), "+f"(d[25]), "+f"(d[26]), "+f"(d[27]), "+f"(d[28]), "+f"(d[29]), "+f"(d[30]), "+f"(d[31]), "+f"(d[32]), "+f"(d[33]), "+f"(d[34]), "+f"(d[35]), "+f"(d[36]), "+f"(d[37]), "+f"(d[38]), "+f"(d[39]), "+f"(d[40]), "+f"(d[41]), "+f"(d[42]), "+f"(d[43]), "+f"(d[44]), "+f"(d[45]), "+f"(d[46]), "+f"(d[47]), "+f"(d[48]), "+f"(d[49]), "+f"(d[50]), "+f"(d[51]), "+f"(d[52]), "+f"(d[53]), "+f"(d[54]), "+f"(d[55]), "+f"(d[56]), "+f"(d[57]), "+f"(d[58]), "+f"(d[59]), "+f"(d[60]), "+f"(d[61]), "+f"(d[62]), "+f"(d[63])
    : "r"(a0), "r"(a1), "r"(a2), "r"(a3), "r"(db));
}
__device__ __forceinline__ void mma_kv_pv_sp_pred(float (&d)[64], uint32_t a0, uint32_t a1, uint32_t a2, uint32_t a3, uint32_t db, uint32_t meta, int sd) {
  asm volatile("{\n.reg .pred p;\n.reg .b64 da, db;\nmov.b64 db, {%68, 0x40000080};\nsetp.ne.b32 p, %70, 0;\n"
    "wgmma.mma_async.sp.sync.aligned.m64n128k32.f32.bf16.bf16 "
    "{%0, %1, %2, %3, %4, %5, %6, %7, %8, %9, %10, %11, %12, %13, %14, %15, %16, %17, %18, %19, %20, %21, %22, %23, %24, %25, %26, %27, %28, %29, %30, %31, %32, %33, %34, %35, %36, %37, %38, %39, %40, %41, %42, %43, %44, %45, %46, %47, %48, %49, %50, %51, %52, %53, %54, %55, %56, %57, %58, %59, %60, %61, %62, %63}, "
    "{%64,%65,%66,%67}, db, %69, 0, p, 1, 1, 1;\n}\n"
    : "+f"(d[0]), "+f"(d[1]), "+f"(d[2]), "+f"(d[3]), "+f"(d[4]), "+f"(d[5]), "+f"(d[6]), "+f"(d[7]), "+f"(d[8]), "+f"(d[9]), "+f"(d[10]), "+f"(d[11]), "+f"(d[12]), "+f"(d[13]), "+f"(d[14]), "+f"(d[15]), "+f"(d[16]), "+f"(d[17]), "+f"(d[18]), "+f"(d[19]), "+f"(d[20]), "+f"(d[21]), "+f"(d[22]), "+f"(d[23]), "+f"(d[24]), "+f"(d[25]), "+f"(d[26]), "+f"(d[27]), "+f"(d[28]), "+f"(d[29]), "+f"(d[30]), "+f"(d[31]), "+f"(d[32]), "+f"(d[33]), "+f"(d[34]), "+f"(d[35]), "+f"(d[36]), "+f"(d[37]), "+f"(d[38]), "+f"(d[39]), "+f"(d[40]), "+f"(d[41]), "+f"(d[42]), "+f"(d[43]), "+f"(d[44]), "+f"(d[45]), "+f"(d[46]), "+f"(d[47]), "+f"(d[48]), "+f"(d[49]), "+f"(d[50]), "+f"(d[51]), "+f"(d[52]), "+f"(d[53]), "+f"(d[54]), "+f"(d[55]), "+f"(d[56]), "+f"(d[57]), "+f"(d[58]), "+f"(d[59]), "+f"(d[60]), "+f"(d[61]), "+f"(d[62]), "+f"(d[63])
    : "r"(a0), "r"(a1), "r"(a2), "r"(a3), "r"(db), "r"(meta), "r"(sd));
}
__device__ __forceinline__ void mma_kv_pv_sp(float (&d)[64], uint32_t a0, uint32_t a1, uint32_t a2, uint32_t a3, uint32_t db, uint32_t meta) {
  asm volatile("{\n.reg .pred p;\n.reg .b64 da, db;\nmov.b64 db, {%68, 0x40000080};\n"
    "wgmma.mma_async.sp.sync.aligned.m64n128k32.f32.bf16.bf16 "
    "{%0, %1, %2, %3, %4, %5, %6, %7, %8, %9, %10, %11, %12, %13, %14, %15, %16, %17, %18, %19, %20, %21, %22, %23, %24, %25, %26, %27, %28, %29, %30, %31, %32, %33, %34, %35, %36, %37, %38, %39, %40, %41, %42, %43, %44, %45, %46, %47, %48, %49, %50, %51, %52, %53, %54, %55, %56, %57, %58, %59, %60, %61, %62, %63}, "
    "{%64,%65,%66,%67}, db, %69, 0, 1, 1, 1, 1;\n}\n"
    : "+f"(d[0]), "+f"(d[1]), "+f"(d[2]), "+f"(d[3]), "+f"(d[4]), "+f"(d[5]), "+f"(d[6]), "+f"(d[7]), "+f"(d[8]), "+f"(d[9]), "+f"(d[10]), "+f"(d[11]), "+f"(d[12]), "+f"(d[13]), "+f"(d[14]), "+f"(d[15]), "+f"(d[16]), "+f"(d[17]), "+f"(d[18]), "+f"(d[19]), "+f"(d[20]), "+f"(d[21]), "+f"(d[22]), "+f"(d[23]), "+f"(d[24]), "+f"(d[25]), "+f"(d[26]), "+f"(d[27]), "+f"(d[28]), "+f"(d[29]), "+f"(d[30]), "+f"(d[31]), "+f"(d[32]), "+f"(d[33]), "+f"(d[34]), "+f"(d[35]), "+f"(d[36]), "+f"(d[37]), "+f"(d[38]), "+f"(d[39]), "+f"(d[40]), "+f"(d[41]), "+f"(d[42]), "+f"(d[43]), "+f"(d[44]), "+f"(d[45]), "+f"(d[46]), "+f"(d[47]), "+f"(d[48]), "+f"(d[49]), "+f"(d[50]), "+f"(d[51]), "+f"(d[52]), "+f"(d[53]), "+f"(d[54]), "+f"(d[55]), "+f"(d[56]), "+f"(d[57]), "+f"(d[58]), "+f"(d[59]), "+f"(d[60]), "+f"(d[61]), "+f"(d[62]), "+f"(d[63])
    : "r"(a0), "r"(a1), "r"(a2), "r"(a3), "r"(db), "r"(meta));
}


struct Params {
  CUtensorMap tx, twq, tk, tv, two, tout, tout2;
  const char* kptr; const char* vptr; const char* woptr; const char* xptr; const char* wqptr; char* outptr;
};

__device__ __forceinline__ int p3_fblk(int cta, int pass) { return ((pass + (cta >> 1)) & 3) * 2; }
__device__ __forceinline__ void issue_wo(const Params& P, int cta, int n, int st) {
  const int pass = n < 4 ? n & 1 : n < 8 ? (n - 4) >> 1 : n >> 2, src = n < 4 ? n >> 1 : n < 8 ? 2 + (n & 1) : n & 3;
  const uint32_t bar = SB + BAR_OFF + 8 * (B_WF + st);
  mbar_expect_tx(bar, 2 * SLOT);
  tma3d(SB + (1 + 2 * st) * SLOT, &P.two, 0, (((cta & 15) ^ (src & 1)) * 2 + (src >> 1)) * 128, p3_fblk(cta, pass), bar);
}

__device__ __forceinline__ void issue_kv(const Params& P, int cta, int i, int slot) {
  const uint32_t bar = SB + BAR_OFF + 8 * (i == 0 ? B_K0 : B_FULL + (((i - 1) >> 1) & 3));
  mbar_expect_tx(bar, SLOT);
  tma_kv(SB + slot * SLOT, (i & 1) ? &P.tv : &P.tk, cta * 256 + (i >> 1) * 8, bar, POL_EVICT_FIRST);
}
__device__ __forceinline__ void xchg_send(int cta, int head) {
  const uint32_t src = SB + QO_OFF + head * QO_HEAD + ((cta & 1) ^ 1) * XCH;
  bulk_store(g_xbuf + (size_t)(cta * 4 + head * 2) * XCH, src, XCH);
  bulk_store(g_xbuf + (size_t)(cta * 4 + head * 2 + 1) * XCH, src + QO_HALF, XCH);
  bulk_commit();
}
__device__ __forceinline__ void xchg_publish(int head) {
  asm volatile("cp.async.bulk.wait_group 0;" ::: "memory");
  asm volatile("mbarrier.arrive.relaxed.cluster.shared::cluster.b64 _, [%0];" ::"r"(SB + BAR_OFF + 8 * (B_XF + head) + (rank_off() ^ (1u << 24))) : "memory");
}
__device__ __forceinline__ void xchg_recv(int cta, int head) {
  mbar_wait(SB + BAR_OFF + 8 * (B_XF + head), 0);
  const uint32_t dst = SB + QO_OFF + head * QO_HEAD + ((cta & 1) ^ 1) * XCH, bar = SB + BAR_OFF + 8 * (B_X + head);
  mbar_expect_tx(bar, 2 * XCH);
  bulk_load(dst, g_xbuf + (size_t)((cta ^ 1) * 4 + head * 2) * XCH, XCH, bar);
  bulk_load(dst + QO_HALF, g_xbuf + (size_t)((cta ^ 1) * 4 + head * 2 + 1) * XCH, XCH, bar);
}

__device__ __forceinline__ void issue_p1(const Params& P, int cta, int c) {
  const int st = (c + 1) % 3;
  const uint32_t bar = SB + BAR_OFF + 8 * (B_P1F + st);
  const uint32_t dst = SB + P1_OFF + st * P1_STAGE;
  mbar_expect_tx(bar, P1_STAGE);
  if (c < 3) {
    tma2d(dst + 32768, &P.tx, c * 64, (cta >> 4) * 224, bar);
    tma2d(dst + 32768 + XCH, &P.tx, c * 64, (cta >> 4) * 224 + 112, bar);
  } else {
    tma2d_mc(dst + 32768 + (cta & 1) * XCH, &P.tx, c * 64, (cta >> 4) * 224 + (cta & 1) * 112, bar);
  }
  tma3d(dst, &P.twq, 0, c * 64, (cta & 15) * 4, bar);
}

constexpr float SM_C = 0.08838834764831845f * 1.4426950408889634f;

constexpr float LAZY_LIMIT = 65536.0f;

__device__ __forceinline__ float quad_sum(float v) { v += __shfl_xor_sync(0xffffffffu, v, 1); return v + __shfl_xor_sync(0xffffffffu, v, 2); }
__device__ __forceinline__ void scale_o(float (&o)[64], float a0, float a1) {
#pragma unroll
  for (int j = 0; j < 16; j++) { o[4 * j] *= a0; o[4 * j + 1] *= a0; o[4 * j + 2] *= a1; o[4 * j + 3] *= a1; }
}
__device__ __forceinline__ void rowmax_dense(const float (&s)[32], float& mx0, float& mx1) {
  mx0 = fmaxf(s[0], s[1]); mx1 = fmaxf(s[2], s[3]);
#pragma unroll
  for (int j = 1; j < 8; j++) {
    mx0 = fmaxf(mx0, fmaxf(s[4 * j], s[4 * j + 1]));
    mx1 = fmaxf(mx1, fmaxf(s[4 * j + 2], s[4 * j + 3]));
  }
  mx0 = fmaxf(mx0, __shfl_xor_sync(0xffffffffu, mx0, 1));
  mx1 = fmaxf(mx1, __shfl_xor_sync(0xffffffffu, mx1, 1));
  mx0 = fmaxf(mx0, __shfl_xor_sync(0xffffffffu, mx0, 2));
  mx1 = fmaxf(mx1, __shfl_xor_sync(0xffffffffu, mx1, 2));
  mx0 *= SM_C; mx1 *= SM_C;
}
__device__ __forceinline__ void exp_dense(const float (&s)[32], uint32_t (&p)[16], const float (&m)[2], float& r0, float& r1) {
#pragma unroll
  for (int j = 0; j < 8; j++) {
    const float e0 = ex2(fmaf(s[4 * j], SM_C, -m[0])), e1 = ex2(fmaf(s[4 * j + 1], SM_C, -m[0]));
    const float e2 = ex2(fmaf(s[4 * j + 2], SM_C, -m[1])), e3 = ex2(fmaf(s[4 * j + 3], SM_C, -m[1]));
    r0 = j ? r0 + (e0 + e1) : e0 + e1; r1 = j ? r1 + (e2 + e3) : e2 + e3;
    p[2 * j] = pack_bf16(e0, e1); p[2 * j + 1] = pack_bf16(e2, e3);
  }
}
template <class F>
__device__ __forceinline__ void softmax_dense(const float (&s)[32], uint32_t (&p)[16], float (&o)[64], float (&m)[2], float (&l)[2], bool newrow, F finish) {
  float r0, r1;
  bool exact = newrow;
#pragma unroll 1
  while (true) {
    if (__builtin_expect(exact, 0)) {
      float mx0, mx1;
      rowmax_dense(s, mx0, mx1);
      if (!newrow) { mx0 = fmaxf(mx0, m[0]); mx1 = fmaxf(mx1, m[1]); }
      const float i0 = rcp(quad_sum(l[0])), i1 = rcp(quad_sum(l[1]));
      const float a0 = newrow ? 0.f : ex2(m[0] - mx0), a1 = newrow ? 0.f : ex2(m[1] - mx1);
      scale_o(o, newrow ? i0 : a0, newrow ? i1 : a1);
      l[0] *= a0; l[1] *= a1;
      if (newrow) finish();
      m[0] = mx0; m[1] = mx1;
    }
    exp_dense(s, p, m, r0, r1);
    if (__builtin_expect(!__any_sync(0xffffffffu, (fmaxf(r0, r1) > LAZY_LIMIT) & !exact), 1)) break;
    exact = true;
  }
  l[0] += r0; l[1] += r1;
}
__device__ __forceinline__ void combine_packed(const float (&s)[32], float (&v)[16]) {
#pragma unroll
  for (int j = 0; j < 8; j++) { v[2 * j] = s[4 * j] + s[4 * j + 2]; v[2 * j + 1] = s[4 * j + 1] + s[4 * j + 3]; }
}
__device__ __forceinline__ float rowmax_packed(const float (&v)[16]) {
  float mx = fmaxf(v[0], v[1]);
#pragma unroll
  for (int j = 1; j < 8; j++) mx = fmaxf(mx, fmaxf(v[2 * j], v[2 * j + 1]));
  mx = fmaxf(mx, __shfl_xor_sync(0xffffffffu, mx, 1));
  mx = fmaxf(mx, __shfl_xor_sync(0xffffffffu, mx, 2));
  return mx * SM_C;
}
__device__ __forceinline__ void exp_packed(const float (&v)[16], uint32_t (&p)[16], float m, float& r, int lane) {
  const bool odd = lane & 1;
  const int t = lane & 3;
  const int src1 = (lane & ~3) | ((t >> 1) | ((t & 1) << 1));
  const int src2 = src1 ^ 1;
#pragma unroll
  for (int j = 0; j < 8; j += 2) {
    const float e0 = ex2(fmaf(v[2 * j], SM_C, -m)), e1 = ex2(fmaf(v[2 * j + 1], SM_C, -m));
    const float e2 = ex2(fmaf(v[2 * j + 2], SM_C, -m)), e3 = ex2(fmaf(v[2 * j + 3], SM_C, -m));
    r = j ? r + ((e0 + e1) + (e2 + e3)) : (e0 + e1) + (e2 + e3);
    const uint32_t x = pack_bf16(e0, e1), y = pack_bf16(e2, e3);
    p[j]     = __shfl_sync(0xffffffffu, odd ? y : x, src1);
    p[j + 1] = __shfl_sync(0xffffffffu, odd ? x : y, src2);
  }
}
template <class F>
__device__ __forceinline__ void softmax_packed(const float (&v)[16], uint32_t (&p)[16], float (&o)[64], float (&m)[2], float (&l)[2], int lane, bool newrow, F finish) {
  float r;
  bool exact = newrow;
#pragma unroll 1
  while (true) {
    if (__builtin_expect(exact, 0)) {
      float mx = rowmax_packed(v);
      if (!newrow) mx = fmaxf(mx, m[0]);
      const float i0 = rcp(quad_sum(l[0]));
      const float a = newrow ? 0.f : ex2(m[0] - mx);
      scale_o(o, newrow ? i0 : a, newrow ? i0 : a);
      l[0] *= a;
      if (newrow) finish();
      m[0] = mx;
    }
    exp_packed(v, p, m[0], r, lane);
    if (__builtin_expect(!__any_sync(0xffffffffu, (r > LAZY_LIMIT) & !exact), 1)) break;
    exact = true;
  }
  l[0] += r;
}
template <int A, int B, int N> __device__ __forceinline__ void fence_range(uint32_t (&r)[N]) {
#pragma unroll
  for (int i = A; i < B; i++) asm volatile("" : "+r"(r[i])::"memory");
}

__device__ __forceinline__ void store_o_dense(const float (&o)[64], uint32_t headbase, int rowbase, int lane) {
  const uint32_t ra = headbase + (rowbase + ((lane >> 3) & 1) * 8 + (lane & 7)) * 128;
  {
#pragma unroll
    for (int j = 0; j < 16; j += 2) {
      const int chunk = (j & 7) + (lane >> 4);
      stsm4(ra + (j >> 3) * QO_HALF + ((chunk ^ (lane & 7)) << 4), pack_bf16(o[4 * j], o[4 * j + 1]), pack_bf16(o[4 * j + 2], o[4 * j + 3]),
            pack_bf16(o[4 * j + 4], o[4 * j + 5]), pack_bf16(o[4 * j + 6], o[4 * j + 7]));
    }
  }
}
__device__ __forceinline__ void store_o_packed(const float (&o)[64], uint32_t headbase, int rowbase, int lane) {
  const uint32_t ra = headbase + (rowbase + (lane & 7)) * 128;
#pragma unroll
  for (int j = 0; j < 16; j += 4) {
    const int chunk = (j & 7) + (lane >> 3);
    uint32_t r[4];
#pragma unroll
    for (int i = 0; i < 4; i++) r[i] = pack_bf16(o[4 * (j + i)] + o[4 * (j + i) + 2], o[4 * (j + i) + 1] + o[4 * (j + i) + 3]);
    stsm4(ra + (j >> 3) * QO_HALF + ((chunk ^ (lane & 7)) << 4), r[0], r[1], r[2], r[3]);
  }
}

template <bool PK> __device__ __forceinline__ void qk_mma(float (&s)[32], uint32_t q, uint32_t k, uint32_t meta) {
  if (PK) {
    mma_kv_qk64_sp_init(s, q, k, meta);
    mma_kv_qk64_sp(s, q + 2, k + 4, meta);
    mma_kv_qk64_sp(s, q + (QO_HALF >> 4), k + 64, meta);
    mma_kv_qk64_sp(s, q + (QO_HALF >> 4) + 2, k + 68, meta);
  } else {
    mma_kv_qk64_init(s, q, k);
#pragma unroll
    for (int i = 1; i < 8; i++) mma_kv_qk64(s, q + (i >> 2) * (QO_HALF >> 4) + 2 * (i & 3), k + (i >> 2) * 64 + 2 * (i & 3));
  }
}
template <bool PK> __device__ __forceinline__ void pv_mma(float (&o)[64], const uint32_t (&p)[16], uint32_t v, int acc, uint32_t meta) {
  if (PK) {
    mma_kv_pv_sp_pred(o, p[0], p[1], p[2], p[3], v, meta, acc);
    mma_kv_pv_sp(o, p[4], p[5], p[6], p[7], v + 512, meta);
  } else {
    mma_kv_pv_pred(o, p[0], p[1], p[2], p[3], v, acc);
#pragma unroll
    for (int i = 1; i < 4; i++) mma_kv_pv(o, p[4 * i], p[4 * i + 1], p[4 * i + 2], p[4 * i + 3], v + 256 * i);
  }
}
__device__ __forceinline__ int tid_now() { int t; asm volatile("mov.u32 %0, %%tid.x;" : "=r"(t)); return t; }
__device__ __forceinline__ int wrap7(int x) { return x >= NSLOT ? x - NSLOT : x; }

template <int WG, bool PK>
__device__ __forceinline__ void store_ob(const float (&ob)[64], uint32_t headbase) {
  const int t = tid_now(), lane = t & 31, wq = (t >> 5) & 3;
  if (PK) store_o_packed(ob, headbase, 192 + wq * 8, lane);
  else store_o_dense(ob, headbase, 64 + wq * 16, lane);
}

template <int WG>
__device__ __forceinline__ void store_oa(const float (&oa)[64], uint32_t headbase) {
  const int t = tid_now();
  store_o_dense(oa, headbase, WG * 128 + ((t >> 5) & 3) * 16, t & 31);
}

__device__ __forceinline__ void service_rare(const Params& P, int role, int j) {
  constexpr uint32_t bars = SB + BAR_OFF;
  const int cta = blockIdx.x;
  if (role < 2) {
    if (role == 0) issue_wo(P, cta, j - 29, j - 29);
    else if (j == 29) mbar_arrive(bars + 8 * (B_FULL + 3));
    return;
  }
  unsigned* cnt = &g_zcnt[(cta >> 4) * 2 + (cta & 1)];
  if (j == 2) {
    char* z = P.outptr + (size_t)((cta >> 4) * 224 + (cta & 1) * 112 + ((cta >> 1) & 7) * 14) * 1024;
    for (int q = 0; q < 7; q++) bulk_store(z + q * 2048, SB + ZERO_OFF, 2048);
    bulk_commit();
  } else if (j == 6) {
    asm volatile("cp.async.bulk.wait_group 0;" ::: "memory");
    asm volatile("red.relaxed.gpu.global.add.u32 [%0], 1;" ::"l"(cnt) : "memory");
  } else if (j == 12) spin_until(cnt, ld_smem(bars + 8 * B_EPOCH));
  else if (j == 28) l2_prefetch(P.woptr + (size_t)cta * 32768, 32768);
  else if (j == 18) xchg_send(cta, 0);
  else if (j == 22) xchg_publish(0);
  else if (j == 26) xchg_recv(cta, 0);
}

template <int WG>
__device__ __forceinline__ void attention(const Params& P, int role) {
  constexpr bool PK = WG == 1;
  constexpr uint32_t bars = SB + BAR_OFF;
  constexpr uint32_t QA = dlo(QO_OFF + WG * 128 * 128, 16), QB = dlo(QO_OFF + (WG == 0 ? 64 : 192) * 128, 16);
  constexpr int NP = PK ? 8 : 16;
  constexpr int MY = 1 + WG, OT = 2 - WG;
  float oa[64], ob[64], sa[32], sb[32];
  uint32_t pa[16], pb[16];
  float ma[2], la[2], mb[2], lb[2];
  ma[0] = ma[1] = mb[0] = mb[1] = 0.f; la[0] = la[1] = lb[0] = lb[1] = 0.f;
#pragma unroll
  for (int i = 0; i < 64; i++) { asm volatile("" : "=f"(oa[i])); asm volatile("" : "=f"(ob[i])); }
  uint32_t meta = 0;
  if (PK) meta = ld_smem(bars + 8 * B_META);
  auto none = [] {};
  if (WG == 1) bar_arrive(OT, 256);
  mbar_wait(bars + 8 * B_K0, 0);
  WG_FENCE();
  qk_mma<false>(sa, QA, dlo(0, 16), meta);
  WG_COMMIT();
  qk_mma<PK>(sb, QB, dlo(0, 16), meta);
  WG_COMMIT();
  WG_WAIT(1);
  fence_regs(sa);
  rowmax_dense(sa, ma[0], ma[1]);
  exp_dense(sa, pa, ma, la[0], la[1]);
  fence_regs(pa);
  mbar_wait(bars + 8 * B_FULL, 0);
  WG_WAIT(0);
  fence_regs(sb);

  int sv = 1;
  static_assert((SB + BAR_OFF + 8 * B_FULL) % 32 == 0, "full barriers must be 32-byte aligned");
  const uint32_t jobs = role == 0 ? 0x1FFFFFFEu : role == 1 ? 0x1FFFFFFFu : 0u;
  const uint32_t rare = role < 2 ? 0x60000000u : role == 2 ? 0x14441044u : 0u;
  uint32_t ldst = SB + (role == 0 ? 6 : 0) * SLOT, lbar = bars + 8 * (B_FULL + 2 + (role & 1));
  int lrow = blockIdx.x * 256 + 24;
  const CUtensorMap* lmap = role == 0 ? &P.tk : &P.tv;
#pragma unroll 1
  for (int j = 0; j < 31; j++) {
    const int sk = wrap7(sv + 1);
    const uint32_t qh = ((j + 1) >> 4) * (QO_HEAD >> 4);
    const uint32_t kd = dlo(0, 16) + sk * (SLOT >> 4), vd = dlo(0, 1024) + sv * (SLOT >> 4);
    const int acc = j & 15;
    auto service = [&] {
      if (((jobs | rare) >> j) & 1) {
        if (elect_one()) {
          if ((jobs >> j) & 1) { mbar_expect_tx(lbar, SLOT); tma_kv(ldst, lmap, lrow, lbar, POL_EVICT_FIRST); }
          else service_rare(P, role, j);
        }
        __syncwarp();
      }
      ldst += 2 * SLOT; ldst = ldst >= SB + NSLOT * SLOT ? ldst - NSLOT * SLOT : ldst;
      lbar = bars + 8 * B_FULL + ((lbar + 8) & 31);
      lrow += 8;
    };
    bar_sync(MY, 256);
    WG_FENCE();
    qk_mma<false>(sa, QA + qh, kd, meta);
    pv_mma<false>(oa, pa, vd, acc, meta);
    WG_COMMIT();
    bar_arrive(OT, 256);
    float v[16];
    int lane = 0;
    if (PK) { combine_packed(sb, v); fence_regs(v); lane = tid_now() & 31; }
    if (WG == 1) service();
    auto fin_b = [&] { if (j) { store_ob<WG, PK>(ob, SB + QO_OFF); fence_async(); } };
    if (PK) softmax_packed(v, pb, ob, mb, lb, lane, acc == 0, fin_b); else softmax_dense(sb, pb, ob, mb, lb, acc == 0, fin_b);
    fence_range<0, NP>(pb); fence_regs(ob); fence_regs(lb);
    WG_WAIT(0);
    fence_regs(sa); fence_regs(oa);
    bar_sync(MY, 256);
    WG_FENCE();
    qk_mma<PK>(sb, QB + qh, kd, meta);
    pv_mma<PK>(ob, pb, vd, acc, meta);
    WG_COMMIT();
    if (WG == 0 || j < 30) bar_arrive(OT, 256);
    const bool ready = mbar_test(bars + 8 * (B_FULL + ((j + 1) & 3)), ((j + 1) >> 2) & 1);
    softmax_dense(sa, pa, oa, ma, la, j == 15, [&] { store_oa<WG>(oa, SB + QO_OFF); });
    fence_regs(pa); fence_regs(oa); fence_regs(la);
    sv = wrap7(sv + 2);
    WG_WAIT(0);
    fence_regs(sb); fence_regs(ob);
    if (!ready) mbar_wait(bars + 8 * (B_FULL + ((j + 1) & 3)), ((j + 1) >> 2) & 1);
  }
  WG_FENCE();
  pv_mma<false>(oa, pa, dlo(0, 1024), 1, meta);
  WG_COMMIT();
  if (PK) { float v[16]; combine_packed(sb, v); softmax_packed(v, pb, ob, mb, lb, tid_now() & 31, false, none); } else softmax_dense(sb, pb, ob, mb, lb, false, none);
  fence_range<0, NP>(pb); fence_regs(ob); fence_regs(lb);
  WG_FENCE();
  pv_mma<PK>(ob, pb, dlo(0, 1024), 1, meta);
  WG_COMMIT();
  WG_WAIT(1);
  fence_regs(oa);
  scale_o(oa, rcp(quad_sum(la[0])), rcp(quad_sum(la[1])));
  store_oa<WG>(oa, SB + QO_OFF + QO_HEAD);
  WG_WAIT(0);
  fence_regs(ob);
  { const float i0 = rcp(quad_sum(lb[0])); scale_o(ob, i0, PK ? i0 : rcp(quad_sum(lb[1]))); }
  store_ob<WG, PK>(ob, SB + QO_OFF + QO_HEAD);
}

__device__ __forceinline__ void store_q(const float (&a)[112], uint32_t half_base, int wq, int lane) {
  const int chunk = 2 * wq + ((lane >> 3) & 1);
  const uint32_t ra = half_base + ((lane >> 4) * 8 + (lane & 7)) * 128 + ((chunk ^ (lane & 7)) << 4);
#pragma unroll
  for (int j = 0; j < 24; j += 2)
    stsm4t(ra + j * 1024, pack_bf16(a[4 * j], a[4 * j + 1]), pack_bf16(a[4 * j + 2], a[4 * j + 3]),
           pack_bf16(a[4 * j + 4], a[4 * j + 5]), pack_bf16(a[4 * j + 6], a[4 * j + 7]));
  {
    const int g = lane >> 2, t = lane & 3;
#pragma unroll
    for (int hi8 = 0; hi8 < 2; hi8++) {
      const int fl = 16 * wq + g + 8 * hi8;
      const int sel = ((fl >> 1) ^ (fl >> 3)) & 1;
      const int c = (fl >> 2) * 2 + (fl & 1);
#pragma unroll
      for (int j = 24; j < 28; j++) {
        const int row = 16 * (j - 24) + 2 * t + 8 * sel;
        const uint32_t ad = half_base + 192 * 128 + row * 64 + ((((c >> 3) ^ (row >> 1)) & 3) << 4) + (c & 7) * 2;
        const uint32_t v = pack_bf16(a[4 * j + 2 * hi8], a[4 * j + 2 * hi8 + 1]);
        asm volatile("{\n.reg .b16 lo, hi;\nmov.b32 {lo, hi}, %1;\nst.shared.u16 [%0], lo;\nst.shared.u16 [%0+64], hi;\n}" ::"r"(ad + rank_off()), "r"(v) : "memory");
      }
    }
  }
}

__global__ void __cluster_dims__(2, 1, 1) __launch_bounds__(256, 1) mha_kernel(const __grid_constant__ Params P) {
  extern __shared__ __align__(1024) uint8_t smem_raw[];
  const int tid = threadIdx.x, lane = tid & 31;
  const int warp = __shfl_sync(0xffffffffu, tid >> 5, 0);
  const int wg = warp >> 2, wq = warp & 3;
  const int cta = blockIdx.x;
  constexpr uint32_t bars = SB + BAR_OFF;

  if (warp == 7 && elect_one()) {
    if (smem_u32(smem_raw) != SB + rank_off()) __trap();
    for (int i = 0; i < 3; i++) mbar_init(bars + 8 * (B_P1F + i), 1);
    fence_async();
    issue_p1(P, cta, 0); issue_p1(P, cta, 1); issue_p1(P, cta, 2);
  }
  if (warp == 5 && elect_one()) {
    for (int i = 0; i < 4; i++) mbar_init(bars + 8 * (B_FULL + i), 2);
    for (int i = B_P1L; i < B_P1E; i++) mbar_init(bars + 8 * i, 8);
    for (int i = B_P1E; i < B_K0; i++) mbar_init(bars + 8 * i, 16);
    for (int i = B_K0; i < B_P1F; i++) mbar_init(bars + 8 * i, 1);
    asm volatile("st.shared.u32 [%0], %1;" ::"r"(bars + 8 * B_META + rank_off()), "r"(META_BITS) : "memory");
    fence_async();
  }
  if (tid == 192) {
    const unsigned v = ld_acquire(&g_zcnt[(cta >> 4) * 2 + (cta & 1)]);
    asm volatile("st.shared.u32 [%0], %1;" ::"r"(bars + 8 * B_EPOCH + rank_off()), "r"((v | 7u) + 1u) : "memory");
  }
  if (tid < 128) { asm volatile("st.shared.v4.u32 [%0], {%1,%1,%1,%1};" ::"r"(SB + ZERO_OFF + tid * 16 + rank_off()), "r"(0) : "memory"); fence_async(); }
  asm volatile("fence.mbarrier_init.release.cluster;" ::: "memory");
  __syncthreads();
  asm volatile("barrier.cluster.arrive.relaxed.aligned;" ::: "memory");
  asm volatile("barrier.cluster.wait.acquire.aligned;" ::: "memory");

  {
    float a0[112], a1[112];
#pragma unroll 1
    for (int c = 0; c < 8; c++) {
      const int st = (c + 1) % 3;
      mbar_wait(bars + 8 * (B_P1F + st), (c / 3) & 1);
      if (c == 0) {
        if (warp == 7 && elect_one()) {
          l2_prefetch(P.wqptr + (size_t)192 * 8192 + (size_t)cta * 20480, 20480);
          l2_prefetch(P.xptr + (size_t)cta * 14336, 14336);
        }
        __syncwarp();
      }
      const uint32_t da = dlo(P1_OFF, 16) + st * (P1_STAGE >> 4) + wg * 1024, db = dlo(P1_OFF + 32768, 16) + st * (P1_STAGE >> 4);
      if (c == 7 && wg == 1) bar_sync(5, 256);
      WG_FENCE();
      mma_proj_pred(a0, da, db, c);
      mma_proj_pred(a1, da + 512, db, c);
#pragma unroll
      for (int k = 1; k < 4; k++) {
        mma_proj(a0, da + 128 * k, db + 2 * k);
        mma_proj(a1, da + 512 + 128 * k, db + 2 * k);
      }
      WG_COMMIT();
      if (c == 7 && wg == 0) bar_arrive(5, 256);
      {
        const int q0 = (int)((PFCUM >> (5 * c)) & 31), q1 = (int)((PFCUM >> (5 * c + 5)) & 31);
        for (int q = q0 + wg; q < q1; q += 2) {
          const int ip = q < 7 ? q : 10 + (q - 7) * 8;
          const char* src = ((ip & 1) ? P.vptr : P.kptr) + ((size_t)cta * 524288 + (size_t)(ip >> 1) * SLOT + (tid & 127) * 128);
          asm volatile("prefetch.global.L2 [%0];" ::"l"(src));
        }
      }
      if (c > 0) {
        WG_WAIT(1);
        const uint32_t eb = bars + 8 * (c < 6 ? B_P1E + c % 3 : B_P1L + c - 6);
        if (lane == 0) { mbar_arrive(eb); if (c < 6) mbar_arrive_peer(eb); }
        if (warp == 7 && elect_one()) {
          mbar_wait(eb, c < 6 ? ((c - 1) / 3) & 1 : 0);
          if (c < 6) { issue_p1(P, cta, c + 2); if (c == 5) { issue_kv(P, cta, 0, 0); issue_kv(P, cta, 1, 1); } }
          else if (c == 6) { issue_kv(P, cta, 2, 2); issue_kv(P, cta, 3, 3); issue_kv(P, cta, 4, 4); issue_kv(P, cta, 5, 5); }
          else issue_kv(P, cta, 6, 6);
        }
        __syncwarp();
      }
    }
    WG_WAIT(0);
    fence_regs(a0); fence_regs(a1);
    if (wg == 0) { bar_arrive(7, 256); mbar_wait(bars + 8 * (B_P1L + 1), 0); bar_sync(3, 128); } else bar_sync(7, 256);
    store_q(a0, SB + QO_OFF + wg * QO_HEAD, wq, lane);
    store_q(a1, SB + QO_OFF + wg * QO_HEAD + QO_HALF, wq, lane);
    fence_async();
    if (wg == 0) { bar_arrive(6, 256); bar_sync(3, 128); } else bar_sync(6, 256);
  }

  if (wg == 0) attention<0>(P, wq ^ 3); else attention<1>(P, wq ^ 3);
  fence_async();
  __syncwarp();
  if (elect_one()) mbar_arrive(bars + 8 * B_O1);

  {
    const int tid = tid_now(), lane = tid & 31;
    const int warp = __shfl_sync(0xffffffffu, tid >> 5, 0);
    const int wg = warp >> 2, wq = warp & 3;
    const int half = cta & 1;
    float a0[56], a1[56], a2[56];
    auto stage_out = [&](float (&a)[56], auto j0, auto j1, uint32_t stage, bool reuse) {
      constexpr int J0 = decltype(j0)::value, J1 = decltype(j1)::value;
      if (reuse) {
        if (wq == 1 && elect_one()) asm volatile("cp.async.bulk.wait_group.read 0;" ::: "memory");
        bar_sync(3 + wg, 128);
      }
      const int chunk = 2 * wq + ((lane >> 3) & 1);
      const uint32_t ro = stage + ((lane >> 4) * 8 + (lane & 7)) * 128 + ((chunk ^ (lane & 7)) << 4);
#pragma unroll
      for (int j = J0; j < J1; j += 2)
        stsm4t(ro + (j - J0) * 1024, pack_bf16(a[4 * j], a[4 * j + 1]), pack_bf16(a[4 * j + 2], a[4 * j + 3]),
               pack_bf16(a[4 * j + 4], a[4 * j + 5]), pack_bf16(a[4 * j + 6], a[4 * j + 7]));
      fence_async();
      if (wq != 1) bar_arrive((J1 - J0 == 14 ? 10 : 8) + wg, 128);
    };
    auto reduce = [&](int parts, int pass, uint32_t stage) {
      if (wq == 1) {
        bar_sync((parts == 3 ? 10 : 8) + wg, 128);
        if (elect_one()) {
          const int col = (p3_fblk(cta, pass) + wg) * 64, row = (cta >> 4) * 224 + half * 112;
          if (parts & 1) tma_red2d(&P.tout, col, row, stage);
          if (parts & 2) tma_red2d(&P.tout2, col, row + 64, stage + (parts & 1) * 8192);
          bulk_commit();
        }
        __syncwarp();
      }
    };
    using I0 = std::integral_constant<int, 0>; using I8 = std::integral_constant<int, 8>; using I14 = std::integral_constant<int, 14>;
    const uint32_t stg = SB + wg * 8192;
    int n = 0, st = 0; uint32_t par = 0;
    auto step = [&](float (&a)[56], int src, int acc, int parts = 0, int pass = 0) {
      mbar_wait(bars + 8 * (B_WF + st), par);
      const uint32_t da = dlo(SLOT, 16) + st * (2 * SLOT >> 4) + wg * 1024;
      const uint32_t db = dlo(QO_OFF, 16) + (src >> 1) * (QO_HEAD >> 4) + ((src ^ half) & 1) * (XCH >> 4);
      WG_FENCE();
      mma_out_pred(a, da, db, acc);
#pragma unroll
      for (int k = 1; k < 8; k++) mma_out(a, da + 128 * k, db + (k >> 2) * (QO_HALF >> 4) + 2 * (k & 3));
      WG_COMMIT();
      if (parts) reduce(parts, pass, stg);
      WG_WAIT(1);
      const int ps = st == 0 ? 2 : st - 1;
      if (n > 0) {
        if (lane == 0) mbar_arrive(bars + 8 * (B_WE + ps));
        if (warp == 7 && n < 14 && elect_one()) {
          mbar_wait(bars + 8 * (B_WE + ps), par ^ (st == 0));
          issue_wo(P, cta, n + 2, ps);
        }
        __syncwarp();
      }
      par ^= (st == 2);
      st = st == 2 ? 0 : st + 1;
      n++;
    };
#pragma unroll 1
    for (int src = 0; src < 2; src++) {
      if (src == 1) mbar_wait(bars + 8 * B_X, 0);
      step(a0, src, src);
      if (warp == 2 && elect_one()) {
        if (src == 0) { mbar_wait(bars + 8 * B_O1, 0); issue_wo(P, cta, 2, 2); xchg_send(cta, 1); }
        else xchg_publish(1);
      }
      __syncwarp();
      step(a1, src, src);
    }
    if (warp == 2 && elect_one()) xchg_recv(cta, 1);
    __syncwarp();
    mbar_wait(bars + 8 * B_O1, 0);
    step(a0, 2, 1);
    mbar_wait(bars + 8 * (B_X + 1), 0);
    step(a0, 3, 1);
    step(a1, 2, 1);       fence_regs(a0); stage_out(a0, I0(), I8(), stg, false);
    step(a1, 3, 1, 1, 0);
    step(a2, 0, 0);       stage_out(a0, I8(), I14(), stg, true);
    step(a2, 1, 1, 2, 0);
    step(a2, 2, 1);       fence_regs(a1); stage_out(a1, I0(), I8(), stg, true);
    step(a2, 3, 1, 1, 1); stage_out(a1, I8(), I14(), stg, true);
    step(a0, 0, 0, 2, 1);
    step(a0, 1, 1);       fence_regs(a2); stage_out(a2, I0(), I8(), stg, true);
    step(a0, 2, 1, 1, 2); stage_out(a2, I8(), I14(), stg, true);
    step(a0, 3, 1, 2, 2);
    WG_WAIT(0);
    fence_regs(a0);
    mbar_wait(bars + 8 * (B_WE + 1), 0);
    stage_out(a0, I0(), I14(), SB + (3 + wg) * SLOT, false);
    reduce(3, 3, SB + (3 + wg) * SLOT);
    if (wq == 1 && elect_one()) asm volatile("cp.async.bulk.wait_group.read 0;" ::: "memory");
    __syncwarp();
  }
}

typedef CUresult (*EncodeFn)(CUtensorMap*, CUtensorMapDataType, cuuint32_t, void*, const cuuint64_t*, const cuuint64_t*,
                             const cuuint32_t*, const cuuint32_t*, CUtensorMapInterleave, CUtensorMapSwizzle,
                             CUtensorMapL2promotion, CUtensorMapFloatOOBfill);

void make_map(EncodeFn fn, CUtensorMap* m, const void* ptr, int rank, const cuuint64_t* dims, const cuuint64_t* strides, const cuuint32_t* box) {
  cuuint32_t es[4] = {1, 1, 1, 1};
  CUresult r = fn(m, CU_TENSOR_MAP_DATA_TYPE_BFLOAT16, rank, const_cast<void*>(ptr), dims, strides, box, es, CU_TENSOR_MAP_INTERLEAVE_NONE,
     CU_TENSOR_MAP_SWIZZLE_128B, CU_TENSOR_MAP_L2_PROMOTION_NONE, CU_TENSOR_MAP_FLOAT_OOB_FILL_NONE);
  (void)r;
}

}

extern "C" void kernel_launch(void* const* d_in, const int* in_sizes, int n_in, void* d_out, int out_size) {
  (void)in_sizes; (void)n_in;
  static EncodeFn fn = nullptr;
  if (!fn) {
    void* f = nullptr; cudaDriverEntryPointQueryResult q;
    cudaGetDriverEntryPoint("cuTensorMapEncodeTiled", &f, cudaEnableDefault, &q);
    fn = (EncodeFn)f;
    cudaFuncSetAttribute(mha_kernel, cudaFuncAttributeMaxDynamicSharedMemorySize, SMEM_BYTES);
  }
  Params P;
  { cuuint64_t d[2] = {512, 1792}, s[1] = {1024}; cuuint32_t b[2] = {64, 112}; make_map(fn, &P.tx, d_in[0], 2, d, s, b); }
  { cuuint64_t d[4] = {64, 8, 2, 32768}, s[3] = {256, 128, 2048}; cuuint32_t b[4] = {64, 8, 2, 8}; make_map(fn, &P.tk, d_in[1], 4, d, s, b); }
  { cuuint64_t d[4] = {64, 8, 2, 32768}, s[3] = {256, 128, 2048}; cuuint32_t b[4] = {64, 8, 2, 8}; make_map(fn, &P.tv, d_in[2], 4, d, s, b); }
  { cuuint64_t d[3] = {64, 512, 64}, s[2] = {8192, 128}; cuuint32_t b[3] = {64, 64, 4}; make_map(fn, &P.twq, d_in[3], 3, d, s, b); }
  { cuuint64_t d[3] = {64, 4096, 8}, s[2] = {1024, 128}; cuuint32_t b[3] = {64, 128, 2}; make_map(fn, &P.two, d_in[4], 3, d, s, b); }
  { cuuint64_t d[2] = {512, 1792}, s[1] = {1024}; cuuint32_t b[2] = {64, 64}; make_map(fn, &P.tout, d_out, 2, d, s, b); b[1] = 48; make_map(fn, &P.tout2, d_out, 2, d, s, b); }
  P.kptr = (const char*)d_in[1]; P.vptr = (const char*)d_in[2]; P.woptr = (const char*)d_in[4]; P.xptr = (const char*)d_in[0]; P.wqptr = (const char*)d_in[3]; P.outptr = (char*)d_out;
  (void)out_size;
  mha_kernel<<<128, 256, SMEM_BYTES, cudaStreamPerThread>>>(P);
}
```
